```python
import torch

def _softmax(x, axis=-1):
    return torch.softmax(x, dim=axis)
def _gelu(x):
    return torch.nn.functional.gelu(x, approximate="tanh")
def _silu(x):
    return torch.nn.functional.silu(x)
def _sigmoid(x):
    return torch.sigmoid(x)
def _layernorm(x, axis=-1, eps=1e-5):
    m = x.mean(dim=axis, keepdim=True)
    v = x.var(dim=axis, keepdim=True, unbiased=False)
    return (x - m) / torch.sqrt(v + eps)
def _scatter_add(tgt, idx, src, axis=0):
    return tgt.clone().index_add_(axis, idx, src)
def _segment_sum(src, seg, n):
    out = torch.zeros((n,) + src.shape[1:], dtype=src.dtype)
    return out.index_add_(0, seg, src)
def _pad(x, pw):
    flat = tuple(v for pair in reversed(pw) for v in pair)
    return torch.nn.functional.pad(x, flat)

kernel_name = 'gated_mix__ssm_conv_s5__dense_activation_mish__prompt'

def setup_inputs():

    _w = (lambda a: (lambda t: t.to(torch.bfloat16) if t.is_floating_point() else t)(torch.as_tensor(a)))
    def _A_setup():
        B, S, D = 1, 2048, 512
        P = D
        Lambda_re = -0.5 * (lambda _x: torch.exp(torch.as_tensor(_x)))((lambda *s: torch.randn(*s, dtype=torch.bfloat16) * 0.2)(P))
        Lambda_im = (lambda *s: torch.randn(*s, dtype=torch.bfloat16) * 0.2)(P) * 1.0
        B_re = (lambda *s: torch.randn(*s, dtype=torch.bfloat16) * 0.2)(P, D) * (D ** -0.5)
        B_im = (lambda *s: torch.randn(*s, dtype=torch.bfloat16) * 0.2)(P, D) * (D ** -0.5)
        C_re = (lambda *s: torch.randn(*s, dtype=torch.bfloat16) * 0.2)(D, P) * (P ** -0.5)
        C_im = (lambda *s: torch.randn(*s, dtype=torch.bfloat16) * 0.2)(D, P) * (P ** -0.5)
        log_dt = (lambda *s: torch.randn(*s, dtype=torch.bfloat16) * 0.2)(P) * 0.3 - 2.0
        Dskip = (lambda *s: torch.randn(*s, dtype=torch.bfloat16) * 0.05)(D)
        return {
            "x": _w((lambda *s: torch.randn(*s, dtype=torch.bfloat16) * 0.05)(B, S, D)),
            "Lambda_re": _w(Lambda_re),
            "Lambda_im": _w(Lambda_im),
            "B_re": _w(B_re),
            "B_im": _w(B_im),
            "C_re": _w(C_re),
            "C_im": _w(C_im),
            "log_dt": _w(log_dt),
            "Dskip": _w(Dskip),
        }
    _A_in = _A_setup()

    def _B_setup():
        B, S, D, F = 1, 2048, 512, 1792
        return {
            "x": _w((lambda *s: torch.randn(*s, dtype=torch.bfloat16) * 0.05)(B, S, D)),
            "w1": _w((lambda *s: torch.randn(*s, dtype=torch.bfloat16) * 3.2)(D, F) * (D ** -0.5)),
            "b1": _w((lambda *s: torch.randn(*s, dtype=torch.bfloat16) * 0.05)(F)),
            "w2": _w((lambda *s: torch.randn(*s, dtype=torch.bfloat16) * 0.05)(F, D) * (F ** -0.5)),
        }
    _B_in = _B_setup()

    return {
        "A_x": _A_in["x"],
        "A_Lambda_re": _A_in["Lambda_re"],
        "A_Lambda_im": _A_in["Lambda_im"],
        "A_B_re": _A_in["B_re"],
        "A_B_im": _A_in["B_im"],
        "A_C_re": _A_in["C_re"],
        "A_C_im": _A_in["C_im"],
        "A_log_dt": _A_in["log_dt"],
        "A_Dskip": _A_in["Dskip"],
        "B_x": _B_in["x"],
        "B_w1": _B_in["w1"],
        "B_b1": _B_in["b1"],
        "B_w2": _B_in["w2"],
        "gate_w": _w((lambda *s: torch.randn(*s, dtype=torch.bfloat16) * 0.05)(512) * 16.0),
    }

def reference(A_x, A_Lambda_re, A_Lambda_im, A_B_re, A_B_im, A_C_re, A_C_im, A_log_dt, A_Dskip, B_x, B_w1, B_b1, B_w2, gate_w):
    def _A_ref(x, Lambda_re, Lambda_im, B_re, B_im, C_re, C_im, log_dt, Dskip):
        Bsz, L, H = x.shape
        Lam = Lambda_re + 1j * Lambda_im
        Bmat = B_re + 1j * B_im
        Cmat = C_re + 1j * C_im
        dt = torch.exp(log_dt)
        Lam_bar = torch.exp(dt * Lam)
        B_bar = ((Lam_bar - 1.0) / Lam)[:, None] * Bmat
        Bu = torch.einsum("bld,pd->blp", x + 0j, B_bar)
        h = torch.zeros_like(Bu[:, 0, :])
        hs = []
        for t in range(L):
            h = Lam_bar[None, :] * h + Bu[:, t, :]
            hs.append(h)
        hseq = torch.stack(hs, 1)
        y = 2.0 * torch.einsum("blp,dp->bld", hseq, Cmat).real + x * Dskip[None, None, :]
        return y

    def _B_ref(x, w1, b1, w2):
        h = torch.einsum("bsd,df->bsf", x, w1) + b1
        sp = torch.log1p(torch.exp(-torch.abs(h))) + torch.where(h > 0, h, torch.zeros_like(h))
        act = h * torch.tanh(sp)
        return torch.einsum("bsf,fd->bsd", act, w2)

    x = A_x
    g = _sigmoid((x * gate_w).sum(-1, keepdims=True))
    a = _A_ref(x, A_Lambda_re, A_Lambda_im, A_B_re, A_B_im, A_C_re, A_C_im, A_log_dt, A_Dskip)
    b = _B_ref(x, B_w1, B_b1, B_w2)
    return g * a + (1 - g) * b
```

```cpp
#include <cuda_runtime.h>
#include <cuda_bf16.h>
#include <cuda.h>
#include <stdint.h>
#include <type_traits>

namespace {

#define FORCE_BMODE2 0
constexpr int LEAD = 1;
constexpr int SLOT = 16384;
constexpr int NSLOT = 14;
constexpr int OFF_BAR = NSLOT * SLOT;
constexpr int OFF_RHO = OFF_BAR + 528;
constexpr int OFF_OG = OFF_RHO + 304;
constexpr int OFF_GW = OFF_OG + 512;
constexpr int OFF_B1 = OFF_GW + 1024;
constexpr int OFF_DS = OFF_B1 + 448;
constexpr int SMEM_BYTES = OFF_DS + 128;
constexpr uint32_t SPIN_LIMIT = 1 << 18;

struct Params {
  const __nv_bfloat16 *b1, *lam_re, *lam_im, *log_dt;
  unsigned* epoch;
  const __nv_bfloat16 *gate_w, *dskip;
  int bmode;
  float2* carry;
  uint4 *gate, *part;
  const __nv_bfloat16 *bre, *bim, *w1, *w2, *cre, *cim;
  CUtensorMap tm_x, tm_w1a, tm_b, tm_w1b, tm_cre, tm_cim, tm_w2a, tm_w2b, tm_out, tm_b2;
};

struct Scratch {
  uint4 part[16 * 8 * 3 * 1024];
  uint4 gate[16 * 64];
  float2 carry[16 * 512];
  unsigned epoch[128];
  unsigned cleared[128 * 8];
};
__device__ __align__(1024) Scratch g_scratch;

template<int TB, int SD = 1> __device__ __forceinline__ void wgmma_ss_n128(float (&d)[64], uint64_t da, uint64_t db) {
  asm volatile("wgmma.mma_async.sync.aligned.m64n128k16.f32.bf16.bf16 {%0,%1,%2,%3,%4,%5,%6,%7,%8,%9,%10,%11,%12,%13,%14,%15,%16,%17,%18,%19,%20,%21,%22,%23,%24,%25,%26,%27,%28,%29,%30,%31,%32,%33,%34,%35,%36,%37,%38,%39,%40,%41,%42,%43,%44,%45,%46,%47,%48,%49,%50,%51,%52,%53,%54,%55,%56,%57,%58,%59,%60,%61,%62,%63}, %64, %65, %67, 1, 1, 0, %66;"
    : "+f"(d[0]), "+f"(d[1]), "+f"(d[2]), "+f"(d[3]), "+f"(d[4]), "+f"(d[5]), "+f"(d[6]), "+f"(d[7]), "+f"(d[8]), "+f"(d[9]), "+f"(d[10]), "+f"(d[11]), "+f"(d[12]), "+f"(d[13]), "+f"(d[14]), "+f"(d[15]), "+f"(d[16]), "+f"(d[17]), "+f"(d[18]), "+f"(d[19]), "+f"(d[20]), "+f"(d[21]), "+f"(d[22]), "+f"(d[23]), "+f"(d[24]), "+f"(d[25]), "+f"(d[26]), "+f"(d[27]), "+f"(d[28]), "+f"(d[29]), "+f"(d[30]), "+f"(d[31]), "+f"(d[32]), "+f"(d[33]), "+f"(d[34]), "+f"(d[35]), "+f"(d[36]), "+f"(d[37]), "+f"(d[38]), "+f"(d[39]), "+f"(d[40]), "+f"(d[41]), "+f"(d[42]), "+f"(d[43]), "+f"(d[44]), "+f"(d[45]), "+f"(d[46]), "+f"(d[47]), "+f"(d[48]), "+f"(d[49]), "+f"(d[50]), "+f"(d[51]), "+f"(d[52]), "+f"(d[53]), "+f"(d[54]), "+f"(d[55]), "+f"(d[56]), "+f"(d[57]), "+f"(d[58]), "+f"(d[59]), "+f"(d[60]), "+f"(d[61]), "+f"(d[62]), "+f"(d[63])
    : "l"(da), "l"(db), "n"(TB), "n"(SD));
}
template<int TB, int SD = 1> __device__ __forceinline__ void wgmma_ss_n96(float (&d)[48], uint64_t da, uint64_t db) {
  asm volatile("wgmma.mma_async.sync.aligned.m64n96k16.f32.bf16.bf16 {%0,%1,%2,%3,%4,%5,%6,%7,%8,%9,%10,%11,%12,%13,%14,%15,%16,%17,%18,%19,%20,%21,%22,%23,%24,%25,%26,%27,%28,%29,%30,%31,%32,%33,%34,%35,%36,%37,%38,%39,%40,%41,%42,%43,%44,%45,%46,%47}, %48, %49, %51, 1, 1, 0, %50;"
    : "+f"(d[0]), "+f"(d[1]), "+f"(d[2]), "+f"(d[3]), "+f"(d[4]), "+f"(d[5]), "+f"(d[6]), "+f"(d[7]), "+f"(d[8]), "+f"(d[9]), "+f"(d[10]), "+f"(d[11]), "+f"(d[12]), "+f"(d[13]), "+f"(d[14]), "+f"(d[15]), "+f"(d[16]), "+f"(d[17]), "+f"(d[18]), "+f"(d[19]), "+f"(d[20]), "+f"(d[21]), "+f"(d[22]), "+f"(d[23]), "+f"(d[24]), "+f"(d[25]), "+f"(d[26]), "+f"(d[27]), "+f"(d[28]), "+f"(d[29]), "+f"(d[30]), "+f"(d[31]), "+f"(d[32]), "+f"(d[33]), "+f"(d[34]), "+f"(d[35]), "+f"(d[36]), "+f"(d[37]), "+f"(d[38]), "+f"(d[39]), "+f"(d[40]), "+f"(d[41]), "+f"(d[42]), "+f"(d[43]), "+f"(d[44]), "+f"(d[45]), "+f"(d[46]), "+f"(d[47])
    : "l"(da), "l"(db), "n"(TB), "n"(SD));
}
template<int TB, int SD> __device__ __forceinline__ void wgmma_rs_n64(float (&d)[32], uint32_t a0, uint32_t a1, uint32_t a2, uint32_t a3, uint64_t db) {
  asm volatile("wgmma.mma_async.sync.aligned.m64n64k16.f32.bf16.bf16 {%0,%1,%2,%3,%4,%5,%6,%7,%8,%9,%10,%11,%12,%13,%14,%15,%16,%17,%18,%19,%20,%21,%22,%23,%24,%25,%26,%27,%28,%29,%30,%31}, {%32,%33,%34,%35}, %36, %38, 1, 1, %37;"
    : "+f"(d[0]), "+f"(d[1]), "+f"(d[2]), "+f"(d[3]), "+f"(d[4]), "+f"(d[5]), "+f"(d[6]), "+f"(d[7]), "+f"(d[8]), "+f"(d[9]), "+f"(d[10]), "+f"(d[11]), "+f"(d[12]), "+f"(d[13]), "+f"(d[14]), "+f"(d[15]), "+f"(d[16]), "+f"(d[17]), "+f"(d[18]), "+f"(d[19]), "+f"(d[20]), "+f"(d[21]), "+f"(d[22]), "+f"(d[23]), "+f"(d[24]), "+f"(d[25]), "+f"(d[26]), "+f"(d[27]), "+f"(d[28]), "+f"(d[29]), "+f"(d[30]), "+f"(d[31])
    : "r"(a0), "r"(a1), "r"(a2), "r"(a3), "l"(db), "n"(TB), "n"(SD));
}
template<int TB, int SD> __device__ __forceinline__ void wgmma_rs_n128(float (&d)[64], uint32_t a0, uint32_t a1, uint32_t a2, uint32_t a3, uint64_t db) {
  asm volatile("wgmma.mma_async.sync.aligned.m64n128k16.f32.bf16.bf16 {%0,%1,%2,%3,%4,%5,%6,%7,%8,%9,%10,%11,%12,%13,%14,%15,%16,%17,%18,%19,%20,%21,%22,%23,%24,%25,%26,%27,%28,%29,%30,%31,%32,%33,%34,%35,%36,%37,%38,%39,%40,%41,%42,%43,%44,%45,%46,%47,%48,%49,%50,%51,%52,%53,%54,%55,%56,%57,%58,%59,%60,%61,%62,%63}, {%64,%65,%66,%67}, %68, %70, 1, 1, %69;"
    : "+f"(d[0]), "+f"(d[1]), "+f"(d[2]), "+f"(d[3]), "+f"(d[4]), "+f"(d[5]), "+f"(d[6]), "+f"(d[7]), "+f"(d[8]), "+f"(d[9]), "+f"(d[10]), "+f"(d[11]), "+f"(d[12]), "+f"(d[13]), "+f"(d[14]), "+f"(d[15]), "+f"(d[16]), "+f"(d[17]), "+f"(d[18]), "+f"(d[19]), "+f"(d[20]), "+f"(d[21]), "+f"(d[22]), "+f"(d[23]), "+f"(d[24]), "+f"(d[25]), "+f"(d[26]), "+f"(d[27]), "+f"(d[28]), "+f"(d[29]), "+f"(d[30]), "+f"(d[31]), "+f"(d[32]), "+f"(d[33]), "+f"(d[34]), "+f"(d[35]), "+f"(d[36]), "+f"(d[37]), "+f"(d[38]), "+f"(d[39]), "+f"(d[40]), "+f"(d[41]), "+f"(d[42]), "+f"(d[43]), "+f"(d[44]), "+f"(d[45]), "+f"(d[46]), "+f"(d[47]), "+f"(d[48]), "+f"(d[49]), "+f"(d[50]), "+f"(d[51]), "+f"(d[52]), "+f"(d[53]), "+f"(d[54]), "+f"(d[55]), "+f"(d[56]), "+f"(d[57]), "+f"(d[58]), "+f"(d[59]), "+f"(d[60]), "+f"(d[61]), "+f"(d[62]), "+f"(d[63])
    : "r"(a0), "r"(a1), "r"(a2), "r"(a3), "l"(db), "n"(TB), "n"(SD));
}
template<int TB, int SD> __device__ __forceinline__ void wgmma_rs_n96(float (&d)[48], uint32_t a0, uint32_t a1, uint32_t a2, uint32_t a3, uint64_t db) {
  asm volatile("wgmma.mma_async.sync.aligned.m64n96k16.f32.bf16.bf16 {%0,%1,%2,%3,%4,%5,%6,%7,%8,%9,%10,%11,%12,%13,%14,%15,%16,%17,%18,%19,%20,%21,%22,%23,%24,%25,%26,%27,%28,%29,%30,%31,%32,%33,%34,%35,%36,%37,%38,%39,%40,%41,%42,%43,%44,%45,%46,%47}, {%48,%49,%50,%51}, %52, %54, 1, 1, %53;"
    : "+f"(d[0]), "+f"(d[1]), "+f"(d[2]), "+f"(d[3]), "+f"(d[4]), "+f"(d[5]), "+f"(d[6]), "+f"(d[7]), "+f"(d[8]), "+f"(d[9]), "+f"(d[10]), "+f"(d[11]), "+f"(d[12]), "+f"(d[13]), "+f"(d[14]), "+f"(d[15]), "+f"(d[16]), "+f"(d[17]), "+f"(d[18]), "+f"(d[19]), "+f"(d[20]), "+f"(d[21]), "+f"(d[22]), "+f"(d[23]), "+f"(d[24]), "+f"(d[25]), "+f"(d[26]), "+f"(d[27]), "+f"(d[28]), "+f"(d[29]), "+f"(d[30]), "+f"(d[31]), "+f"(d[32]), "+f"(d[33]), "+f"(d[34]), "+f"(d[35]), "+f"(d[36]), "+f"(d[37]), "+f"(d[38]), "+f"(d[39]), "+f"(d[40]), "+f"(d[41]), "+f"(d[42]), "+f"(d[43]), "+f"(d[44]), "+f"(d[45]), "+f"(d[46]), "+f"(d[47])
    : "r"(a0), "r"(a1), "r"(a2), "r"(a3), "l"(db), "n"(TB), "n"(SD));
}

__device__ __forceinline__ void wg_fence() { asm volatile("wgmma.fence.sync.aligned;" ::: "memory"); }
__device__ __forceinline__ void wg_commit() { asm volatile("wgmma.commit_group.sync.aligned;" ::: "memory"); }
template <int N> __device__ __forceinline__ void wg_wait() { asm volatile("wgmma.wait_group.sync.aligned %0;" ::"n"(N) : "memory"); }
template <int N> __device__ __forceinline__ void reg_fence(float (&d)[N]) {
#pragma unroll
  for (int i = 0; i < N; i++) asm volatile("" : "+f"(d[i])::"memory");
}
template <int N> __device__ __forceinline__ void reg_fence(uint32_t (&d)[N]) {
#pragma unroll
  for (int i = 0; i < N; i++) asm volatile("" : "+r"(d[i])::"memory");
}
template <int LBO, int SBO, int SWZ> __device__ __forceinline__ uint64_t mkdesc(uint32_t a16, int off) {
  uint32_t lo = a16 + (uint32_t)((off >> 4) + ((LBO >> 4) << 16));
  uint32_t hi = (uint32_t)(SBO >> 4) | ((uint32_t)SWZ << 30);
  return ((uint64_t)hi << 32) | lo;
}
__device__ __forceinline__ void mbar_init(uint32_t bar, uint32_t cnt) { asm volatile("mbarrier.init.shared::cta.b64 [%0], %1;" ::"r"(bar), "r"(cnt) : "memory"); }
__device__ __forceinline__ void mbar_expect_tx(uint32_t bar, uint32_t bytes) { asm volatile("mbarrier.arrive.expect_tx.shared::cta.b64 _, [%0], %1;" ::"r"(bar), "r"(bytes) : "memory"); }
__device__ __forceinline__ void mbar_arrive(uint32_t bar) { asm volatile("mbarrier.arrive.shared::cta.b64 _, [%0];" ::"r"(bar) : "memory"); }
__device__ __forceinline__ void mbar_arrive_cl(uint32_t bar) { asm volatile("mbarrier.arrive.shared::cluster.b64 _, [%0];" ::"r"(bar) : "memory"); }
__device__ __forceinline__ void mbar_wait_(uint32_t bar, uint32_t parity, uint32_t& spins) {
  asm volatile(
      "{\n.reg .pred p;\n"
      "LAB_WAIT:\n.pragma \"nounroll\";\n"
      "mbarrier.try_wait.parity.shared::cta.b64 p, [%1], %2;\n"
      "@p bra LAB_DONE;\n"
      "add.u32 %0, %0, 1;\n"
      "setp.lt.u32 p, %0, %3;\n"
      "@p bra LAB_WAIT;\n"
      "LAB_DONE:\n}" : "+&r"(spins) : "r"(bar), "r"(parity), "n"(SPIN_LIMIT) : "memory");
}
#define mbar_wait(bar, parity) mbar_wait_(bar, parity, spins)
__device__ __forceinline__ void pin_(uint32_t& spins) {
  asm volatile("{\n.reg .pred p;\nLAB_PIN:\n.pragma \"nounroll\";\nsetp.eq.u32 p, %0, 0xffffffff;\n@p add.u32 %0, %0, 1;\n@p bra LAB_PIN;\n}" : "+r"(spins)::"memory");
}
#define PIN() pin_(spins)
__device__ __forceinline__ bool elect_one() {
  uint32_t p;
  asm volatile("{\n.reg .pred P;\nelect.sync _|P, 0xffffffff;\nselp.u32 %0, 1, 0, P;\n}" : "=r"(p));
  return p;
}
__device__ __forceinline__ void tma2d(uint32_t dst, const CUtensorMap* m, int c0, int c1, uint32_t bar) {
  asm volatile("cp.async.bulk.tensor.2d.shared::cluster.global.mbarrier::complete_tx::bytes [%0], [%1, {%3, %4}], [%2];"
               ::"r"(dst), "l"(m), "r"(bar), "r"(c0), "r"(c1) : "memory");
}
__device__ __forceinline__ void tma3d(uint32_t dst, const CUtensorMap* m, int c0, int c1, int c2, uint32_t bar) {
  asm volatile("cp.async.bulk.tensor.3d.shared::cluster.global.mbarrier::complete_tx::bytes [%0], [%1, {%3, %4, %5}], [%2];"
               ::"r"(dst), "l"(m), "r"(bar), "r"(c0), "r"(c1), "r"(c2) : "memory");
}
__device__ __forceinline__ void tma4d(uint32_t dst, const CUtensorMap* m, int c0, int c3, uint32_t bar) {
  asm volatile("cp.async.bulk.tensor.4d.shared::cluster.global.mbarrier::complete_tx::bytes [%0], [%1, {%3, %5, %5, %4}], [%2];"
               ::"r"(dst), "l"(m), "r"(bar), "r"(c0), "r"(c3), "r"(0) : "memory");
}
__device__ __forceinline__ void tma5d(uint32_t dst, const CUtensorMap* m, int c0, int c3, int c4, uint32_t bar) {
  asm volatile("cp.async.bulk.tensor.5d.shared::cluster.global.mbarrier::complete_tx::bytes [%0], [%1, {%3, %5, %5, %6, %4}], [%2];"
               ::"r"(dst), "l"(m), "r"(bar), "r"(c0), "r"(c4), "r"(0), "r"(c3) : "memory");
}
__device__ __forceinline__ void bulk_g2s(uint32_t dst, const void* src, uint32_t bytes, uint32_t bar) {
  asm volatile("cp.async.bulk.shared::cluster.global.mbarrier::complete_tx::bytes [%0], [%1], %2, [%3];" ::"r"(dst), "l"(src), "r"(bytes), "r"(bar) : "memory");
}
__device__ __forceinline__ void l2_prefetch(const void* src, uint32_t bytes) { asm volatile("cp.async.bulk.prefetch.L2.global [%0], %1;" ::"l"(src), "r"(bytes) : "memory"); }
__device__ __forceinline__ void prefetch_tm(const CUtensorMap* m) { asm volatile("prefetch.tensormap [%0];" ::"l"(m) : "memory"); }
__device__ __forceinline__ uint32_t pack_bf16(float lo, float hi) {
  uint32_t r;
  asm("cvt.rn.bf16x2.f32 %0, %1, %2;" : "=r"(r) : "f"(hi), "f"(lo));
  return r;
}
__device__ __forceinline__ float bf_lo(uint32_t w) { return __uint_as_float(w << 16); }
__device__ __forceinline__ float bf_hi(uint32_t w) { return __uint_as_float(w & 0xffff0000u); }
__device__ __forceinline__ uint32_t bf_mul2(uint32_t a, uint32_t b) {
  uint32_t r;
  asm("mul.rn.bf16x2 %0, %1, %2;" : "=r"(r) : "r"(a), "r"(b));
  return r;
}
__device__ __forceinline__ uint32_t bf_add2(uint32_t a, uint32_t b) {
  uint32_t r;
  asm("add.rn.bf16x2 %0, %1, %2;" : "=r"(r) : "r"(a), "r"(b));
  return r;
}
__device__ __forceinline__ float bf_round(float x) { return __bfloat162float(__float2bfloat16_rn(x)); }
__device__ __forceinline__ float ex2(float x) { float r; asm("ex2.approx.ftz.f32 %0, %1;" : "=f"(r) : "f"(x)); return r; }
__device__ __forceinline__ float rcp(float x) { float r; asm("rcp.approx.ftz.f32 %0, %1;" : "=f"(r) : "f"(x)); return r; }
__device__ __forceinline__ float rcp_full(float x) { float r; asm("rcp.approx.f32 %0, %1;" : "=f"(r) : "f"(x)); return r; }
__device__ __forceinline__ uint4 lds128(uint32_t a) {
  uint4 v;
  asm volatile("ld.shared.v4.u32 {%0,%1,%2,%3}, [%4];" : "=r"(v.x), "=r"(v.y), "=r"(v.z), "=r"(v.w) : "r"(a) : "memory");
  return v;
}
__device__ __forceinline__ uint32_t lds32(uint32_t a) { uint32_t v; asm volatile("ld.shared.u32 %0, [%1];" : "=r"(v) : "r"(a) : "memory"); return v; }
__device__ __forceinline__ void ldsm4(uint32_t& r0, uint32_t& r1, uint32_t& r2, uint32_t& r3, uint32_t a) {
  asm volatile("ldmatrix.sync.aligned.m8n8.x4.shared.b16 {%0,%1,%2,%3}, [%4];" : "=r"(r0), "=r"(r1), "=r"(r2), "=r"(r3) : "r"(a) : "memory");
}
__device__ __forceinline__ void stsm4_t(uint32_t a, uint32_t r0, uint32_t r1, uint32_t r2, uint32_t r3) {
  asm volatile("stmatrix.sync.aligned.m8n8.x4.trans.shared.b16 [%0], {%1,%2,%3,%4};" ::"r"(a), "r"(r0), "r"(r1), "r"(r2), "r"(r3) : "memory");
}
__device__ __forceinline__ void st_x128(uint4* p, uint32_t a, uint32_t b, uint32_t c, uint32_t d) {
  asm volatile("st.relaxed.gpu.global.v4.b32 [%0], {%1, %2, %3, %4};" ::"l"(p), "r"(a), "r"(b), "r"(c), "r"(d) : "memory");
}
__device__ __forceinline__ void ld_x128(const uint4* p, uint32_t& a, uint32_t& b, uint32_t& c, uint32_t& d) {
  asm volatile("ld.relaxed.gpu.global.v4.b32 {%0, %1, %2, %3}, [%4];" : "=r"(a), "=r"(b), "=r"(c), "=r"(d) : "l"(p) : "memory");
}
__device__ __forceinline__ uint32_t set_tag(uint32_t w, uint32_t tag) {
  uint32_t r;
  asm("lop3.b32 %0, %1, 0xfffffffe, %2, 0xea;" : "=r"(r) : "r"(w), "r"(tag));
  return r;
}
__device__ __forceinline__ uint32_t stale2(uint32_t a, uint32_t b, uint32_t tag) {
  uint32_t r;
  asm("lop3.b32 %0, %1, %2, %3, 0x7e;" : "=r"(r) : "r"(a), "r"(b), "r"(tag));
  return r;
}
__device__ __forceinline__ bool any_stale(uint32_t a, uint32_t b, uint32_t c, uint32_t d, uint32_t tag) {
  uint32_t r;
  asm volatile("{\n.reg .b32 x, y;\n.reg .pred p;\nlop3.b32 x, %1, %2, %5, 0x7e;\nlop3.b32 y, %3, %4, %5, 0x7e;\nlop3.b32 x, x, y, 1, 0xa8;\n"
               "setp.ne.u32 p, x, 0;\nvote.sync.any.pred p, p, 0xffffffff;\nselp.u32 %0, 1, 0, p;\n}"
               : "=r"(r) : "r"(a), "r"(b), "r"(c), "r"(d), "r"(tag));
  return r;
}
__device__ __forceinline__ void st_x64(float2* p, uint32_t a, uint32_t b) {
  asm volatile("{\n.reg .b64 v;\nmov.b64 v, {%1, %2};\nst.relaxed.gpu.global.b64 [%0], v;\n}" ::"l"(p), "r"(a), "r"(b) : "memory");
}
template <int K> __device__ __forceinline__ void ld_x64_gt(const float2* p, int n, uint32_t& a, uint32_t& b) {
  asm volatile("{\n.reg .pred p;\nsetp.gt.s32 p, %3, %4;\n@p ld.relaxed.gpu.global.v2.b32 {%0, %1}, [%2];\n}"
               : "+r"(a), "+r"(b) : "l"(p), "r"(n), "n"(K) : "memory");
}

struct cplx { float r, i; };
__device__ __forceinline__ cplx cfma(cplx a, cplx b, cplx c) {
  return {fmaf(a.r, b.r, fmaf(-a.i, b.i, c.r)), fmaf(a.r, b.i, fmaf(a.i, b.r, c.i))};
}
__device__ __forceinline__ cplx cmul(cplx a, cplx b) { return {fmaf(a.r, b.r, -a.i * b.i), fmaf(a.r, b.i, a.i * b.r)}; }
__device__ __forceinline__ cplx csq(cplx a) { return {fmaf(a.r, a.r, -a.i * a.i), 2.f * a.r * a.i}; }
template <int D> __device__ __forceinline__ cplx cup(cplx a) { return {__shfl_up_sync(0xffffffffu, a.r, D, 4), __shfl_up_sync(0xffffffffu, a.i, D, 4)}; }
template <int D> __device__ __forceinline__ cplx cxor_add(cplx a) { return {a.r + __shfl_xor_sync(0xffffffffu, a.r, D), a.i + __shfl_xor_sync(0xffffffffu, a.i, D)}; }

template <int V> using IC = std::integral_constant<int, V>;
template <int I, int E, class F> __device__ __forceinline__ void sfor(F&& f) {
  if constexpr (I < E) { f(std::integral_constant<int, I>{}); sfor<I + 1, E>(f); }
}
__device__ __forceinline__ uint32_t mapa(uint32_t a, uint32_t cta) { uint32_t r; asm("mapa.shared::cluster.u32 %0, %1, %2;" : "=r"(r) : "r"(a), "r"(cta)); return r; }
__device__ __forceinline__ void bar_sync(int id) { asm volatile("bar.sync %0, 256;" ::"r"(id) : "memory"); }
__device__ __forceinline__ void bar_arrive(int id) { asm volatile("bar.arrive %0, 256;" ::"r"(id) : "memory"); }

__device__ __forceinline__ float mish1(float h) {
  const float e = ex2(h * 1.4426950408889634f);
  return fmaf(h, rcp(fmaf(e, fmaf(e, -0.5f, -1.f), -1.f)), h);
}
template <int P0, int P1, int N> __device__ __forceinline__ void mish_range(const float (&acc)[N], uint32_t (&act)[N / 2]) {
#pragma unroll
  for (int c = P0; c < P1; c++) act[c] = pack_bf16(mish1(acc[2 * c]), mish1(acc[2 * c + 1]));
#pragma unroll
  for (int c = P0; c < P1; c++) asm volatile("" : "+r"(act[c]));
}
__host__ __device__ constexpr uint32_t rslot(int u) { return 8 + (u + 2) % 6; }
__host__ __device__ constexpr uint32_t p2_slot(int st, int part) {
  return st == 0 ? (part == 0 ? 8 : 9 + part) : st == 1 ? (part == 0 ? 9 : 3 + part) : (part == 2 ? 6 : 12 + part);
}
__host__ __device__ constexpr int p2_k(int ps) { return ps < 3 ? (3 - ps) % 3 : ps < 6 ? ps - 3 : 3; }
__host__ __device__ constexpr int p2_own(int ps) { return (0xB8 >> ps) & 1; }
__host__ __device__ constexpr int p2_src(int k) { return k < 2 ? k : k == 2 ? 7 : 2; }
__device__ __forceinline__ int p2_blk(int ps, int jj, int rank) { return 2 * ((jj + 1 + p2_k(ps)) & 3) + (rank ^ p2_own(ps) ^ 1); }

__global__ void __cluster_dims__(2, 1, 1) __launch_bounds__(384, 1) fused_kernel(const __grid_constant__ Params p) {
  extern __shared__ __align__(1024) unsigned char smem_raw[];
  const uint32_t sb = (uint32_t)__cvta_generic_to_shared(smem_raw);
  const uint32_t full = sb + OFF_BAR, empty = full + 8 * NSLOT, stg = empty + 8 * NSLOT;
  const uint32_t bar_gate = stg + 64, bar_h = bar_gate + 8, bar_rdy = bar_gate + 16, bar_src = bar_gate + 24, bar_small = bar_gate + 40,
                 bar_bias = bar_gate + 48, bar_first = bar_gate + 56, bar_out = bar_gate + 64, fullb = bar_out + 112;
  const int rank = blockIdx.x & 1;
  int gp, gn;
  {
    const int t = ((blockIdx.x >> 1) + 60) & 63, u = t & 31, u7 = (u * 37) >> 8, r = u - 7 * u7;
    gp = t < 32 ? t & 7 : u7 == 4 ? 0 : 1 + r;
    gn = t < 32 ? t >> 3 : 4 + (u7 == 4 ? r : u7);
  }
  const int jj = gp >> 1, j = 2 * jj + rank;
  const int ti = (gp & 1) * 8 + gn;
  const int fa = 224 * j + (rank ? 96 : 0);
  const int fb = 224 * j + (rank ? 0 : 128);
  auto xslot = [&](int kb) { const int t = (kb - 2 * jj - 2) & 7; return t >= 6 ? t ^ rank ^ 1 : t; };
  auto xblock = [&](int s) { return ((s >= 6 ? s ^ rank ^ 1 : s) + 2 * jj + 2) & 7; };
  auto load_x = [&](int kb, int half, uint32_t bar) { tma5d(sb + xslot(kb) * SLOT + half * 8192, &p.tm_x, kb * 64, 8 * half, ti, bar); };
  auto load_a = [&](uint32_t dst, int kb, int half, uint32_t bar) { tma3d(dst + half * 8192, &p.tm_w1a, 0, kb * 64 + 32 * half, fa >> 6, bar); };

  if (threadIdx.x < 32) {
    if (elect_one()) {
      mbar_init(bar_first, 1); mbar_init(full + 8 * xslot(0), 1); mbar_init(full + 8 * rslot(0), 1);
      asm volatile("fence.mbarrier_init.release.cluster;" ::: "memory");
      mbar_expect_tx(bar_first, SLOT);
      load_x(0, LEAD, bar_first);
      load_a(sb + rslot(0) * SLOT, 0, 0, bar_first);
      mbar_expect_tx(full + 8 * xslot(0), 8192);
      load_x(0, LEAD ^ 1, full + 8 * xslot(0));
      mbar_expect_tx(full + 8 * rslot(0), 8192);
      load_a(sb + rslot(0) * SLOT, 0, 1, full + 8 * rslot(0));
    }
  } else if (threadIdx.x < 64) {
    if (elect_one()) {
      mbar_init(bar_bias, 1);
      asm volatile("fence.mbarrier_init.release.cluster;" ::: "memory");
      mbar_expect_tx(bar_bias, 448);
      bulk_g2s(sb + OFF_B1, p.b1 + 224 * j, 448, bar_bias);
    }
  }
  __syncwarp();
  const int warp = __shfl_sync(0xffffffffu, (int)(threadIdx.x >> 5), 0);
  const int lane = __shfl_xor_sync(0xffffffffu, (int)(threadIdx.x & 31), 0);
  uint32_t spins = 0;

  if (warp >= 8) {
    asm volatile("setmaxnreg.dec.sync.aligned.u32 24;");
    if (elect_one()) {
      if (warp == 8) {
#pragma unroll
        for (int s = 1; s < 8; s++) mbar_init(full + 8 * ((xslot(0) + s) & 7), 1);
#pragma unroll
        for (int s = 1; s < 6; s++) mbar_init(full + 8 * rslot(s), 1);
      } else if (warp == 9) {
        mbar_init(bar_small, 1);
        mbar_init(bar_gate, 2); mbar_init(bar_h, 8); mbar_init(bar_rdy, 17); mbar_init(bar_src, 2); mbar_init(bar_src + 8, 2);
#pragma unroll
        for (int s = 0; s < 8; s++) mbar_init(fullb + 8 * s, 1);
      } else {
        const uint32_t b0 = warp == 10 ? empty : bar_out, cnt = warp == 10 ? 2 : 4, s0 = stg + 32 * (warp - 10);
#pragma unroll
        for (int s = 0; s < 14; s++) mbar_init(b0 + 8 * s, cnt);
#pragma unroll
        for (int s = 0; s < 4; s++) mbar_init(s0 + 8 * s, 1);
#pragma unroll
        for (int s = 0; s < 4; s++) mbar_expect_tx(s0 + 8 * s, 8192);
      }
      asm volatile("fence.mbarrier_init.release.cluster;" ::: "memory");
    }
    __syncwarp();
    asm volatile("barrier.cluster.arrive.relaxed.aligned;" ::: "memory");
    if (warp == 8) {
      asm volatile("bar.arrive 3, 384;" ::: "memory");
      if (elect_one()) {
#pragma unroll 1
        for (int kb = 1; kb < 8; kb++) {
          const uint32_t xb = full + 8 * xslot(kb);
          mbar_expect_tx(xb, SLOT);
          load_x(kb, 0, xb); load_x(kb, 1, xb);
          if (kb < 6) {
            const uint32_t s0 = kb < 4 ? 10 + kb : 4 + kb;
            mbar_expect_tx(full + 8 * s0, SLOT); load_a(sb + s0 * SLOT, kb, 0, full + 8 * s0); load_a(sb + s0 * SLOT, kb, 1, full + 8 * s0);
          }
        }
        prefetch_tm(&p.tm_b); prefetch_tm(&p.tm_w1b); prefetch_tm(&p.tm_cre); prefetch_tm(&p.tm_cim); prefetch_tm(&p.tm_w2a); prefetch_tm(&p.tm_w2b); prefetch_tm(&p.tm_out);
      }
      __syncwarp();
      if ((sb & 0x3FFFFu) != 1024) __trap();
      asm volatile("bar.sync 4, 64;" ::: "memory");
      uint32_t s0 = rslot(6);
#pragma unroll 1
      for (int u = 6; u < 16; u++) {
        const uint32_t dst = sb + s0 * SLOT, bar = full + 8 * s0;
        mbar_wait(empty + 8 * s0, u >= 12);
        if (elect_one()) {
          mbar_expect_tx(bar, SLOT);
          const int k0 = xblock(u & 7) * 64;
          if (u < 8) { load_a(dst, u, 0, bar); load_a(dst, u, 1, bar); }
          else if (p.bmode != 2) tma4d(dst, &p.tm_b, k0, 8 * j, bar);
          else {
#pragma unroll 1
            for (int g = 0; g < 16; g++) tma2d(dst + g * 1024, (g & 1) ? &p.tm_b2 : &p.tm_b, k0, 64 * j + 8 * (g >> 1), bar);
          }
        }
        if (++s0 == NSLOT) s0 = 8;
      }
#pragma unroll 1
      for (int s = 0; s < 8; s++) {
        const int last = (12 * s + 11) >> 4;
        mbar_wait(empty + 64 + 8 * last, last < 2);
        if (elect_one()) { mbar_expect_tx(fullb + 8 * s, 12288); tma3d(sb + 8 * SLOT + s * 12288, &p.tm_w1b, 0, xblock(s) * 64, fb >> 5, fullb + 8 * s); }
      }
      auto load2 = [&](int ps, int st, int part, uint32_t bar) {
        const uint32_t dst = sb + p2_slot(st, part) * SLOT;
        const int col = p2_blk(ps, jj, rank) * 64;
        if (part == 0) tma2d(dst, &p.tm_w2a, col, fa, bar);
        if (part == 1) { tma2d(dst, &p.tm_cre, 64 * j, col, bar); tma2d(dst + 8192, &p.tm_cim, 64 * j, col, bar); }
        if (part == 2) tma2d(dst, &p.tm_w2b, col, fb, bar);
      };
#pragma unroll
      for (int u = 0; u < 6; u++) {
        const uint32_t sl = p2_slot(u & 1, u >> 1), bar = (sl < 8 ? fullb : full) + 8 * sl;
        mbar_wait(empty + 8 * sl, sl >= 10);
        if (elect_one()) { mbar_expect_tx(bar, u >= 4 ? 12288 : SLOT); load2(u & 1, u & 1, u >> 1, bar); }
      }
      auto stage = [&](int ps, int st) {
        if (elect_one()) {
          mbar_expect_tx(full + 8 * p2_slot(st, 0), 2 * SLOT + 12288);
#pragma unroll
          for (int part = 0; part < 3; part++) load2(ps, st, part, full + 8 * p2_slot(st, 0));
        }
      };
      mbar_wait(empty + 8 * 13, 1);
      stage(2, 2);
#pragma unroll
      for (int part = 0; part < 3; part++) {
        mbar_wait(empty + 8 * p2_slot(0, part), part == 0);
        if (elect_one()) {
          if (part == 0) { mbar_expect_tx(full + 8 * 8, 2 * SLOT); mbar_expect_tx(full + 8 * 9, 2 * SLOT + 12288); }
          if (part == 2) mbar_expect_tx(full + 8 * 11, 12288);
          load2(3, 0, part, full + 8 * (part == 2 ? 11 : 8));
          load2(4, 1, part, full + 8 * 9);
        }
      }
      mbar_wait(empty + 8 * 12, 0); stage(5, 2);
      mbar_wait(empty + 8 * 8, 0); stage(6, 0);
      mbar_wait(empty + 8 * 9, 1); stage(7, 1);
    } else if (warp < 11) {
      if (warp == 10) asm volatile("bar.arrive 4, 64;" ::: "memory");
      asm volatile("bar.sync 3, 384;" ::: "memory");
      if (warp == 9 && elect_one()) {
        mbar_expect_tx(bar_small, 1024 + 128);
        bulk_g2s(sb + OFF_GW, p.gate_w, 1024, bar_small);
        bulk_g2s(sb + OFF_DS, p.dskip + 64 * j, 128, bar_small);
      }
      __syncwarp();
      const uint32_t epoch = __ldcg(&p.epoch[blockIdx.x]), tag = (epoch + 1) & 1;
      const uint32_t row = 16 * j + 8 * (warp - 9) + (lane >> 2);
      mbar_wait(bar_small, 0);
      mbar_wait(bar_first, 0);
      const uint32_t grow = sb + row * 128, gsw = (row & 7) ^ ((lane & 3) << 1), gwa = sb + OFF_GW + (lane & 3) * 32;
      float gsum = 0.f;
#pragma unroll 1
      for (int kb = 0; kb < 8; kb++) {
        mbar_wait(full + 8 * xslot(kb), 0);
#pragma unroll
        for (int c = 0; c < 2; c++) {
          const uint4 xv = lds128(grow + xslot(kb) * SLOT + ((gsw ^ c) << 4));
          const uint4 gv = lds128(gwa + kb * 128 + c * 16);
          const uint32_t m0 = bf_mul2(xv.x, gv.x), m1 = bf_mul2(xv.y, gv.y), m2 = bf_mul2(xv.z, gv.z), m3 = bf_mul2(xv.w, gv.w);
          gsum += ((bf_lo(m0) + bf_hi(m0)) + (bf_lo(m1) + bf_hi(m1))) + ((bf_lo(m2) + bf_hi(m2)) + (bf_lo(m3) + bf_hi(m3)));
        }
      }
      gsum += __shfl_xor_sync(0xffffffffu, gsum, 1);
      gsum += __shfl_xor_sync(0xffffffffu, gsum, 2);
      const float g = bf_round(rcp(1.f + ex2(-1.4426950408889634f * bf_round(gsum))));
      float og = fmaxf(bf_round(1.f - g), 8.673617379884035e-19f);
      const float rho = bf_round(g * rcp(og));
      if (g > 0.5f) og = g * rcp(rho);
      const float og1 = __shfl_down_sync(0xffffffffu, og, 4), rho1 = __shfl_down_sync(0xffffffffu, rho, 4);
      if ((lane & 7) == 0)
        st_x128(&p.gate[ti * 64 + (row >> 1)], set_tag(__float_as_uint(rho), tag), __float_as_uint(rho1), __float_as_uint(og), __float_as_uint(og1));
      const int pr = 32 * (warp - 9) + lane;
      uint32_t v0, v1, v2, v3;
#pragma unroll 1
      do ld_x128(&p.gate[ti * 64 + pr], v0, v1, v2, v3);
      while (__any_sync(0xffffffffu, (v0 ^ tag) & 1) && ++spins < SPIN_LIMIT);
      asm volatile("st.shared.b32 [%0], %1;" ::"r"(sb + OFF_RHO + 4 * ((pr & 3) * 20 + (pr >> 2))), "r"(__byte_perm(v0, v1, 0x7632)) : "memory");
      asm volatile("st.shared.v2.b32 [%0], {%1, %2};" ::"r"(sb + OFF_OG + 8 * pr), "r"(v2), "r"(v3) : "memory");
      __syncwarp();
      if (lane == 0) mbar_arrive(bar_gate);
      const int w = warp - 9;
      const uint32_t peer_sb = mapa(sb, rank ^ 1);
      asm volatile("barrier.cluster.wait.aligned;" ::: "memory");
#pragma unroll 1
      for (int i = 0; i < 7; i++) {
        const int ps = 0x6541320 >> (4 * i) & 7, k = p2_k(ps);
        const bool own = p2_own(ps);
        const uint4* gdst = p.part + ((ti * 8 + p2_blk(ps, jj, rank)) * 3 + k) * 1024 + 512 * w;
        uint32_t src = sb + 8192 * w + (own ? k ^ 2 : p2_src(k)) * SLOT, dst = peer_sb + 8192 * w + (k ^ 2) * SLOT,
                 dbar = peer_sb + (OFF_BAR + 16 * NSLOT) + 16 * k + 8 * w;
        asm volatile("" : "+l"(gdst), "+r"(src), "+r"(dst), "+r"(dbar));
        if (own) {
          mbar_wait(bar_out + 16 * ps + 8 * w, 0);
          asm volatile("fence.proxy.async.shared::cta;" ::: "memory");
          if (elect_one()) {
            asm volatile("cp.async.bulk.global.shared::cta.bulk_group [%0], [%1], 8192;" ::"l"(gdst), "r"(src) : "memory");
            asm volatile("cp.async.bulk.commit_group;" ::: "memory");
            if (ps != 3) asm volatile("cp.async.bulk.wait_group.read 0;" ::: "memory");
            if (ps == 4) { mbar_arrive(bar_src + 8 * w); if (w == 0) p.epoch[blockIdx.x] = epoch + 1; }
          }
        } else {
          mbar_wait(bar_out + 16 * ps + 8 * w, 0);
          asm volatile("fence.proxy.async.shared::cta;" ::: "memory");
          if (elect_one())
            asm volatile("cp.async.bulk.shared::cluster.shared::cta.mbarrier::complete_tx::bytes [%0], [%1], 8192, [%2];" ::"r"(dst), "r"(src), "r"(dbar) : "memory");
        }
        __syncwarp();
      }
      mbar_wait(stg + 48 + 8 * w, 0);
      if (lane < 2) mbar_arrive_cl(mapa(bar_src + 8 * w, rank ^ 1));
      mbar_wait(bar_src + 8 * w, 1);
    } else {
      asm volatile("bar.sync 3, 384;" ::: "memory");
      mbar_wait(full + 8 * xslot(1), 0);
      if (elect_one()) { l2_prefetch(p.bre + blockIdx.x * 2048, 4096); l2_prefetch(p.bim + blockIdx.x * 2048, 4096); l2_prefetch(p.w1 + blockIdx.x * 7168, 14336); }
      mbar_wait(full + 8 * xslot(7), 0);
      if (elect_one()) { l2_prefetch(p.w2 + blockIdx.x * 7168, 14336); l2_prefetch(p.cre + blockIdx.x * 2048, 4096); l2_prefetch(p.cim + blockIdx.x * 2048, 4096); }
      const uint32_t launch = __ldcg(&p.epoch[blockIdx.x]) + 1;
      const int to = ti * 8 + p2_blk(5, jj, rank);
#pragma unroll 1
      for (int v = 0; v < 32; v++) { st_x128(p.part + (to * 3 + 2) * 1024 + 32 * v + lane, 0, 0, 0, 0); __nanosleep(0); }
      asm volatile("fence.acq_rel.gpu;\nfence.proxy.async.global;" ::: "memory");
      __syncwarp();
      if (lane == 0) {
        asm volatile("fence.acq_rel.gpu;\nst.relaxed.gpu.global.b32 [%0], %1;" ::"l"(p.epoch + 128 + 8 * to), "r"(launch) : "memory");
        mbar_arrive(bar_rdy);
      }
      mbar_wait(bar_h, 0);
      uint32_t v;
#pragma unroll 1
      do asm volatile("ld.acquire.gpu.global.b32 %0, [%1];" : "=r"(v) : "l"(p.epoch + 128 + 8 * (ti * 8 + j)) : "memory");
      while (v != launch && ++spins < SPIN_LIMIT);
      if (lane < 2) mbar_arrive(bar_src + 8 * lane);
    }
  } else {
    const int q = lane & 3, w = warp >> 2;
    const int ch = 64 * j + 8 * warp + (lane >> 2);
    uint32_t epoch;
    uint16_t raw_re, raw_im, raw_dt;
    asm volatile("ld.global.nc.u16 %0, [%1];" : "=h"(raw_re) : "l"(p.lam_re + ch));
    asm volatile("ld.global.nc.u16 %0, [%1];" : "=h"(raw_im) : "l"(p.lam_im + ch));
    asm volatile("ld.global.nc.u16 %0, [%1];" : "=h"(raw_dt) : "l"(p.log_dt + ch));
    asm volatile("ld.global.cg.u32 %0, [%1];" : "=r"(epoch) : "l"(p.epoch + blockIdx.x) : "memory");
    asm volatile("setmaxnreg.inc.sync.aligned.u32 240;");
    asm volatile("barrier.cluster.arrive.relaxed.aligned;" ::: "memory");
    constexpr uint32_t db = 1024 >> 4;
    const uint32_t tag = (epoch + 1) & 1;
    const bool rel = (threadIdx.x & 127) == 0;
    auto release = [&](uint32_t slot) { if (rel) mbar_arrive(empty + 8 * slot); };
    float accS[64] = {}, accA[64], accB[48];
    asm volatile("bar.sync 3, 384;" ::: "memory");
    {
      const uint32_t k0 = q == 0 ? 0x3F80u : 0u, k7 = q == 3 ? 0x3F800000u : 0u, zero = lane >> 5;
      const uint32_t ua = rank ? k7 : k0, ub = rank ? k0 : k7;
      mbar_wait(bar_bias, 0);
      wg_fence();
      wgmma_rs_n128<1, 0>(accA, ua, ua, zero, zero, mkdesc<0, 16, 0>(db + (OFF_B1 >> 4) + 5 * rank, 0));
      wgmma_rs_n96<1, 0>(accB, ub, ub, zero, zero, mkdesc<0, 16, 0>(db + (OFF_B1 >> 4) + 9 - 9 * rank, 0));
      wg_commit();
    }

    cplx lam1, ks1, ks2, lamq, mu, muq;
    float dt, lam2i, m00, m01, m10, m11;
    float2* cpub;

    sfor<0, 8>([&](auto kc) {
      constexpr int kb = decltype(kc)::value;
      const uint32_t xs = db + xslot(kb) * 1024 + w * 512, ws = db + rslot(kb) * 1024;
      auto mma = [&](int kk) { wgmma_ss_n128<1, 1>(accA, mkdesc<16, 1024, 1>(xs, kk * 32), mkdesc<4096, 1024, 1>(ws, (kk >> 1) * 8192 + (kk & 1) * 2048)); };
      if constexpr (kb == 0) {
        mbar_wait(bar_first, 0);
        if (w != LEAD) mbar_wait(full + 8 * xslot(0), 0);
        wg_fence(); mma(0); mma(1); wg_commit();
        mbar_wait(full + 8 * rslot(0), 0);
        wg_fence(); mma(2); mma(3); wg_commit();
      } else {
        mbar_wait(full + 8 * xslot(kb), 0);
        mbar_wait(full + 8 * rslot(kb), kb / 6);
        if constexpr (kb == 7) { if (w != LEAD) bar_sync(5); }
        wg_fence(); mma(0); mma(1); mma(2); mma(3); wg_commit();
        wg_wait<1>();
        release(rslot(kb - 1));
      }
      if constexpr (kb == 1) mbar_wait(full + 8 * xslot(0), 0);
      if constexpr (kb >= 2 && kb < 7) PIN();
      if constexpr (kb == 1) {
        cpub = &p.carry[ti * 512 + ch];
        dt = bf_round(expf(bf_lo(raw_dt)));
        asm volatile("" : "+l"(cpub), "+f"(dt));
      }
      if constexpr (kb == 2) {
        sincospif(dt * bf_lo(raw_im) * 0.318309886183790672f, &lam1.i, &lam1.r);
        asm volatile("" : "+f"(lam1.r), "+f"(lam1.i));
      }
      if constexpr (kb == 3) {
        const float mag = expf(dt * bf_lo(raw_re));
        lam1 = {mag * lam1.r, mag * lam1.i};
        asm volatile("" : "+f"(lam1.r), "+f"(lam1.i));
        asm volatile("barrier.cluster.wait.aligned;" ::: "memory");
      }
      if constexpr (kb == 4) {
        const float is = rcp_full(fmaxf(fabsf(bf_lo(raw_re)), fabsf(bf_lo(raw_im))));
        const float lre = bf_lo(raw_re) * is, lim = bf_lo(raw_im) * is, inv = 2.f * rcp(lre * lre + lim * lim);
        const float nr = lam1.r - 1.f, ni = lam1.i;
        const float cr = (nr * lre + ni * lim) * inv * is, ci = (ni * lre - nr * lim) * inv * is;
        lam2i = -lam1.i;
        const bool sw = p.bmode == 1;
        if (sw) lam1.i = -lam1.i;
        m00 = sw ? -ci : cr; m01 = sw ? cr : -ci; m10 = sw ? -cr : -ci; m11 = sw ? -ci : -cr;
        asm volatile("" : "+f"(m00), "+f"(m01), "+f"(m10), "+f"(m11), "+f"(lam1.i), "+f"(lam2i));
      }
      if constexpr (kb == 5) {
        ks1 = csq(csq(csq(csq(csq(lam1)))));
        ks2 = csq(ks1);
        mu = csq(ks2);
        asm volatile("" : "+f"(ks1.r), "+f"(ks1.i), "+f"(ks2.r), "+f"(ks2.i), "+f"(mu.r), "+f"(mu.i));
      }
      if constexpr (kb == 6) {
        const cplx one = {1.f, 0.f}, zero = {0.f, 0.f};
        const cplx mu4 = csq(csq(mu)), mu8 = csq(mu4);
        lamq = cmul((q & 1) ? ks1 : one, (q & 2) ? ks2 : one);
        muq = cmul((q & 1) ? mu4 : one, (q & 2) ? mu8 : one);
        if (q < 1) ks1 = zero;
        if (q < 2) ks2 = zero;
        asm volatile("" : "+f"(ks1.r), "+f"(ks1.i), "+f"(ks2.r), "+f"(ks2.i), "+f"(lamq.r), "+f"(lamq.i), "+f"(muq.r), "+f"(muq.i));
      }
    });

    uint32_t actA[32], actB[24], hf[32];
    uint32_t cr[4] = {}, ci[4] = {};
    cplx seg;
    auto U = [&](int t) { return cplx{accS[4 * (t >> 1) + (t & 1)], accS[4 * (t >> 1) + 2 + (t & 1)]}; };
    auto carry_load = [&]() {
      const float2* src = cpub - (1 + 4 * q) * 512;
      ld_x64_gt<0>(src, ti - 4 * q, cr[0], ci[0]); ld_x64_gt<1>(src - 512, ti - 4 * q, cr[1], ci[1]);
      ld_x64_gt<2>(src - 1024, ti - 4 * q, cr[2], ci[2]); ld_x64_gt<3>(src - 1536, ti - 4 * q, cr[3], ci[3]);
    };
    cplx h = {0.f, 0.f};
    auto scan2 = [&](auto c0c, auto c1c) {
      const cplx lam2 = {lam1.r, lam2i};
#pragma unroll
      for (int c = decltype(c0c)::value; c < decltype(c1c)::value; c++) {
        uint32_t g0, g1;
        asm volatile("ld.shared.v2.b32 {%0, %1}, [%2];" : "=r"(g0), "=r"(g1) : "r"(sb + OFF_RHO + 4 * (q * 20 + 2 * c)) : "memory");
        cplx y[4];
#pragma unroll
        for (int t = 0; t < 4; t++) y[t] = h = cfma(lam2, h, U(4 * c + t));
        hf[4 * c] = bf_mul2(pack_bf16(y[0].r, y[1].r), g0); hf[4 * c + 1] = bf_mul2(pack_bf16(y[0].i, y[1].i), g0);
        hf[4 * c + 2] = bf_mul2(pack_bf16(y[2].r, y[3].r), g1); hf[4 * c + 3] = bf_mul2(pack_bf16(y[2].i, y[3].i), g1);
        asm volatile("" : "+r"(hf[4 * c]), "+r"(hf[4 * c + 1]), "+r"(hf[4 * c + 2]), "+r"(hf[4 * c + 3]));
      }
    };
    sfor<0, 16>([&](auto sc) {
      constexpr int s = decltype(sc)::value, u = 8 + s;
      constexpr uint32_t ws = s < 8 ? db + rslot(u) * 1024 : db + 8 * 1024 + (s - 8) * 768, xs = db + (s & 7) * 1024;
      if constexpr (s < 8) mbar_wait(full + 8 * rslot(u), (u / 6) & 1);
      else mbar_wait(fullb + 8 * (s & 7), 0);
      wg_fence();
      if constexpr (s < 8) {
        wgmma_ss_n128<0, s != 0>(accS, mkdesc<16, 1024, 1>(ws + w * 512, 0), mkdesc<16, 1024, 1>(xs, 0));
#pragma unroll
        for (int kk = 1; kk < 4; kk++) wgmma_ss_n128<0, 1>(accS, mkdesc<16, 1024, 1>(ws + w * 512, kk * 32), mkdesc<16, 1024, 1>(xs, kk * 32));
      } else {
#pragma unroll
        for (int kk = 0; kk < 4; kk++) wgmma_ss_n96<1>(accB, mkdesc<16, 1024, 1>(xs + w * 512, kk * 32), mkdesc<4096, 512, 2>(ws, kk * 1024));
      }
      wg_commit();
      if constexpr (s == 0) { if (w == LEAD) bar_arrive(5); }
      auto retire = [&]() {
        if constexpr (s != 9) wg_wait<1>();
        if constexpr (s <= 8) release(rslot(u - 1));
        if constexpr (s >= 10 && s != 13) release(s < 13 ? s - 2 : s - 3);
        if constexpr (s == 13) mbar_wait(bar_gate, 0);
        if constexpr (s == 10 || s == 13 || s == 14) release(s - 9);
      };
      if constexpr ((s & 7) == 0) retire();
      if constexpr (s == 0) reg_fence(accA);
      if constexpr (s < 8) mish_range<4 * s, 4 * s + 4>(accA, actA);
      if constexpr (s == 8) { reg_fence(accS); seg = U(0); }
      if constexpr (s == 8 || s == 9) {
#pragma unroll
        for (int t = s == 8 ? 1 : 17; t < (s == 8 ? 17 : 32); t++) seg = cfma(lam1, seg, U(t));
        asm volatile("" : "+f"(seg.r), "+f"(seg.i));
      }
      if constexpr (s == 9) {
        seg = cfma(ks1, cup<1>(seg), seg);
        seg = cfma(ks2, cup<2>(seg), seg);
        if (q == 3) st_x64(cpub, set_tag(__float_as_uint(seg.r), tag), __float_as_uint(seg.i));
        seg = cup<1>(seg);
        if (q == 0) seg = {0.f, 0.f};
        asm volatile("" : "+f"(seg.r), "+f"(seg.i));
      }
      if constexpr (s > 9 && s < 15) {
#pragma unroll
        for (int t = (s - 10) * 32 / 5; t < (s - 9) * 32 / 5; t++) {
          const int a = 4 * (t >> 1) + (t & 1);
          const float u0 = accS[a], u1 = accS[a + 2];
          accS[a] = fmaf(m00, u0, m01 * u1);
          accS[a + 2] = fmaf(m10, u0, m11 * u1);
          asm volatile("" : "+f"(accS[a]), "+f"(accS[a + 2]));
        }
      }
      if constexpr (s == 13) {
#pragma unroll
        for (int k = 0; k < 4; k++) { cr[k] = tag; ci[k] = 0; }
        carry_load();
      }
      if constexpr (s == 15) {
#pragma unroll 1
        while (any_stale(cr[0], cr[1], cr[2], cr[3], tag)) {
          if (++spins >= SPIN_LIMIT) break;
          carry_load();
        }
        h = {__uint_as_float(cr[3]), __uint_as_float(ci[3])};
#pragma unroll
        for (int k = 2; k >= 0; k--) h = cfma(mu, h, cplx{__uint_as_float(cr[k]), __uint_as_float(ci[k])});
        h = cfma(lamq, cxor_add<2>(cxor_add<1>(cmul(muq, h))), seg);
        h = {fmaf(m00, h.r, m01 * h.i), fmaf(m10, h.r, m11 * h.i)};
        asm volatile("" : "+f"(h.r), "+f"(h.i));
        PIN();
        scan2(IC<0>{}, IC<4>{});
      }
      if constexpr ((s & 7) != 0) retire();
    });
    auto store_h = [&]() {
      const uint32_t hst = sb + ((lane >> 3) & 1) * SLOT + ((lane >> 4) * 8 + (lane & 7)) * 128 + ((warp ^ (lane & 7)) << 4);
      mbar_wait(empty + 8, 0);
#pragma unroll
      for (int c = 0; c < 8; c++) stsm4_t(hst + c * 2048, hf[4 * c], hf[4 * c + 1], hf[4 * c + 2], hf[4 * c + 3]);
      __syncwarp();
      if (lane == 0) mbar_arrive(bar_h);
    };

    float acc[32], sum[32], blk0[32];
    const uint32_t arow = sb + (16 * warp + (lane & 15)) * 128, asw = (lane & 7) ^ (lane >> 4);
    auto mmaA = [&](float (&d)[32], uint32_t slot, auto s0c, auto s1c) {
      sfor<decltype(s0c)::value, decltype(s1c)::value>([&](auto sc) {
        constexpr int s = decltype(sc)::value;
        wgmma_rs_n64<1, s != 0>(d, actA[4 * s], actA[4 * s + 1], actA[4 * s + 2], actA[4 * s + 3], mkdesc<16, 1024, 1>(db + slot * 1024, s * 2048));
      });
    };
    auto mmaC = [&](float (&d)[32], uint32_t slot, int s0, int s1) {
#pragma unroll
      for (int s = s0; s < s1; s++) wgmma_rs_n64<0, 1>(d, hf[4 * s], hf[4 * s + 1], hf[4 * s + 2], hf[4 * s + 3], mkdesc<16, 1024, 1>(db + slot * 1024, (s >> 2) * 8192 + (s & 3) * 32));
    };
    auto mmaB = [&](float (&d)[32], uint32_t slot, int s0, int s1) {
#pragma unroll
      for (int s = s0; s < s1; s++) wgmma_rs_n64<1, 1>(d, actB[4 * s], actB[4 * s + 1], actB[4 * s + 2], actB[4 * s + 3], mkdesc<16, 1024, 1>(db + slot * 1024, s * 2048));
    };
    const uint32_t xl = sb + 2048 * warp + 16 * lane, outb = bar_out + 8 * w;
    sfor<0, 13>([&](auto bc) {
      constexpr int b = decltype(bc)::value, h4 = 4 * (b & 1);
      constexpr int MB[14] = {0, 0, 2, 4, 6, 9, 11, 13, 15, 18, 20, 22, 24, 24};
      if constexpr (b == 0) mbar_wait(full + 8 * 8, 0);
      if constexpr (b == 2) mbar_wait(full + 8 * 9, 0);
      if constexpr (b == 4) mbar_wait(full + 8 * 10, 1);
      if constexpr (b == 6) mbar_wait(fullb + 8 * 4, 1);
      if constexpr (b == 8) mbar_wait(full + 8 * 12, 1);
      if constexpr (b == 10) { mbar_wait(full + 8 * 11, 1); mbar_wait(fullb + 8 * 5, 1); }
      wg_fence();
      if constexpr (b < 2) mmaA(blk0, 8, IC<h4>{}, IC<h4 + 4>{});
      else if constexpr (b < 4) mmaA(sum, 9, IC<h4>{}, IC<h4 + 4>{});
      else if constexpr (b < 6) mmaC(blk0, 10, h4, h4 + 4);
      else if constexpr (b < 8) mmaC(sum, 4, h4, h4 + 4);
      else if constexpr (b < 10) mmaA(acc, 12, IC<h4>{}, IC<h4 + 4>{});
      else { mmaB(blk0, 11, 2 * (b - 10), 2 * (b - 9)); mmaB(sum, 5, 2 * (b - 10), 2 * (b - 9)); }
      wg_commit();
      if constexpr (b == 0) { wg_wait<1>(); release(13); reg_fence(accB); }
      if constexpr (b == 0) { scan2(IC<4>{}, IC<8>{}); store_h(); }
      if constexpr (b == 3) {
        mbar_wait(bar_h, 0);
#pragma unroll
        for (int s = 0; s < 8; s++) ldsm4(hf[4 * s], hf[4 * s + 1], hf[4 * s + 2], hf[4 * s + 3], arow + (s >> 2) * SLOT + ((asw ^ (2 * (s & 3))) << 4));
      }
      if constexpr (b == 4) {
        wg_wait<1>();
        release(8);
        if (lane < 2) mbar_arrive_cl(mapa(bar_rdy, lane));
      }
      if constexpr (b == 8) { wg_wait<1>(); release(10); }
      mish_range<MB[b], MB[b + 1]>(accB, actB);
    });

    uint32_t pl[16], pg[16] = {}, ph[16] = {}, oa[4];
    auto put = [&](int slot, int ps) {
#pragma unroll
      for (int v = 0; v < 4; v++)
        asm volatile("st.shared.v4.b32 [%0], {%1, %2, %3, %4};" ::"r"(xl + slot * SLOT + v * 512), "r"(pl[4 * v]), "r"(pl[4 * v + 1]), "r"(pl[4 * v + 2]), "r"(pl[4 * v + 3]) : "memory");
      __syncwarp();
      if (lane == 0) mbar_arrive(outb + 16 * ps);
    };
    auto send_peer = [&](float (&d)[32], int ps) {
      reg_fence(d);
#pragma unroll
      for (int v = 0; v < 16; v++) pl[v] = pack_bf16(d[2 * v], d[2 * v + 1]);
      put(p2_src(p2_k(ps)), ps);
    };
    auto load_peer = [&](int k) {
      mbar_wait(stg + 16 * k + 8 * w, 0);
#pragma unroll
      for (int v = 0; v < 4; v++) { const uint4 t = lds128(xl + (k ^ 2) * SLOT + v * 512); pl[4 * v] = t.x; pl[4 * v + 1] = t.y; pl[4 * v + 2] = t.z; pl[4 * v + 3] = t.w; }
    };
    const uint4* psrc = p.part + (ti * 8 + j) * 3 * 1024 + 128 * warp + lane;
    auto load_part = [&](uint32_t (&x)[16], int sl) {
#pragma unroll
      for (int v = 0; v < 4; v++) ld_x128(psrc + sl * 1024 + v * 32, x[4 * v], x[4 * v + 1], x[4 * v + 2], x[4 * v + 3]);
    };
    auto add_sum = [&](float o0, float o1, auto first) {
#pragma unroll
      for (int v = 0; v < 32; v++) {
        const float x = (v & 1) ? bf_hi(pg[v >> 1]) : bf_lo(pg[v >> 1]), o = (v & 2) ? o1 : o0;
        sum[v] = decltype(first)::value ? x * o : fmaf(x, o, sum[v]);
      }
      reg_fence(sum);
    };
    const float og0 = __uint_as_float(lds32(sb + OFF_OG + 4 * (16 * warp + (lane >> 2)))), og1 = __uint_as_float(lds32(sb + OFF_OG + 32 + 4 * (16 * warp + (lane >> 2))));
    const uint32_t ob = sb + 12 * SLOT + 4096 * warp;

    sfor<2, 8>([&](auto pc) {
      constexpr int ps = decltype(pc)::value, st = ps % 3, k = p2_k(ps);
      constexpr bool own = p2_own(ps);
      constexpr uint32_t sA = p2_slot(st, 0), sC = p2_slot(st, 1), sB = p2_slot(st, 2);
      if constexpr (ps > 2) mbar_wait(full + 8 * sA, ((ps / 3) & 1) ^ (sA == 12));
      if (ps > 2 || w != LEAD) bar_sync(1 + w);
      wg_fence();
      if constexpr (ps == 7) load_part(pg, 2);
      if constexpr (ps > 2) mmaA(acc, sA, IC<0>{}, IC<8>{});
      mmaC(acc, sC, 0, 8);
      if constexpr (ps == 2) { wg_commit(); wg_wait<1>(); release(11); wg_fence(); }
      if constexpr (ps == 3) { wg_commit(); mbar_wait(full + 8 * sB, 0); wg_fence(); }
      mmaB(acc, sB, 0, 6);
      wg_commit();
      if (ps < 7 || w == LEAD) bar_arrive(2 - w);
      if constexpr (ps == 2) {
        mbar_wait(bar_rdy, 0);
        send_peer(blk0, 0);
#pragma unroll
        for (int s = 0; s < 4; s++)
          ldsm4(pg[4 * s], pg[4 * s + 1], pg[4 * s + 2], pg[4 * s + 3], arow + 7 * SLOT + ((asw ^ (2 * s)) << 4));
      }
      if constexpr (ps == 6) {
#pragma unroll
        for (int c = 0; c < 4; c++) oa[c] = ob + (lane >> 2) * 128 + 8 * (q & 1) + (((q >> 1) ^ (lane >> 2) ^ (2 * c)) << 4);
        reg_fence(oa);
        mbar_wait(bar_src + 8 * w, 0);
      }
      if constexpr (own) load_peer(k);
      if constexpr (ps == 4) {
        const uint32_t ra = sb + OFF_RHO + 4 * ((lane >> 3) * 20 + 2 * warp), sh = (lane & 4) ? 0 : 16;
        add_sum(bf_hi(lds32(ra) << sh) * og0, bf_hi(lds32(ra + 4) << sh) * og1, IC<1>{});
        PIN();
      }
      if constexpr (ps == 7) {
#pragma unroll 1
        while (any_stale(stale2(ph[0], ph[4], tag), stale2(ph[8], ph[12], tag), ~(pg[0] & pg[4]), ~(pg[8] & pg[12]), 0)) {
          if (++spins >= SPIN_LIMIT) break;
          load_part(ph, 1); load_part(pg, 2);
        }
#pragma unroll
        for (int v = 0; v < 16; v++) pl[v] = bf_add2(bf_add2(pl[v], ph[v]), pg[v]);
        return;
      }
      wg_wait<0>();
      if (ps < 5) release(sA);
      if constexpr (own) {
        reg_fence(acc);
#pragma unroll
        for (int v = 0; v < 16; v++) ph[v] = pack_bf16(acc[2 * v], acc[2 * v + 1]);
#pragma unroll
        for (int v = 0; v < 16; v++) pl[v] = bf_add2(ph[v], pl[v]);
#pragma unroll
        for (int v = 0; v < 4; v++) pl[4 * v] = k == 2 ? pl[4 * v] | 1 : set_tag(pl[4 * v], tag);
        put(k ^ 2, ps);
      } else {
        send_peer(acc, ps);
      }
      if constexpr (ps == 2) {
#pragma unroll
        for (int s = 0; s < 4; s++) {
          const uint32_t d0 = lds32(sb + OFF_DS + 32 * s + 4 * q), d1 = lds32(sb + OFF_DS + 32 * s + 16 + 4 * q);
          pg[4 * s] = bf_mul2(pg[4 * s], d0); pg[4 * s + 1] = bf_mul2(pg[4 * s + 1], d0);
          pg[4 * s + 2] = bf_mul2(pg[4 * s + 2], d1); pg[4 * s + 3] = bf_mul2(pg[4 * s + 3], d1);
        }
        reg_fence(pg);
      }
      if constexpr (ps == 3) send_peer(sum, 1);
      if constexpr (ps == 5) load_part(pg, 0);
      if constexpr (ps == 6) {
#pragma unroll 1
        while (any_stale(pg[0], pg[4], pg[8], pg[12], tag)) {
          if (++spins >= SPIN_LIMIT) break;
          load_part(pg, 0);
        }
        add_sum(og0, og1, IC<0>{});
        PIN();
        load_part(ph, 1);
      }
    });
    wg_wait<0>();
    reg_fence(acc);
    auto fin = [&](int i) { return fmaf(acc[i] + ((i & 1) ? bf_hi(pl[i >> 1]) : bf_lo(pl[i >> 1])), (i & 2) ? og1 : og0, sum[i]); };
#pragma unroll
    for (int hh = 0; hh < 2; hh++) {
#pragma unroll
      for (int c = 4 * hh; c < 4 * hh + 4; c++) {
        asm volatile("st.shared.v2.f32 [%0], {%1, %2};" ::"r"(oa[c & 3] + hh * 2048), "f"(fin(4 * c)), "f"(fin(4 * c + 1)) : "memory");
        asm volatile("st.shared.v2.f32 [%0], {%1, %2};" ::"r"(oa[c & 3] + hh * 2048 + 1024), "f"(fin(4 * c + 2)), "f"(fin(4 * c + 3)) : "memory");
      }
      asm volatile("fence.proxy.async.shared::cta;" ::: "memory");
      __syncwarp();
      if (elect_one())
        asm volatile("cp.async.bulk.tensor.5d.global.shared::cta.bulk_group [%0, {%2, %5, %5, %3, %4}], [%1];"
                     ::"l"(&p.tm_out), "r"(ob + hh * 2048), "r"(64 * j + 32 * hh), "r"(2 * warp), "r"(ti), "r"(0) : "memory");
      if (hh == 0) PIN();
    }
    if (elect_one()) {
      asm volatile("cp.async.bulk.commit_group;" ::: "memory");
      asm volatile("cp.async.bulk.wait_group.read 0;" ::: "memory");
    }
    if (spins == 0xffffffffu) p.epoch[blockIdx.x] = 0;
  }
}

typedef CUresult (*EncodeFn)(CUtensorMap*, CUtensorMapDataType, cuuint32_t, void*, const cuuint64_t*, const cuuint64_t*, const cuuint32_t*,
                             const cuuint32_t*, CUtensorMapInterleave, CUtensorMapSwizzle, CUtensorMapL2promotion, CUtensorMapFloatOOBfill);

void encode(EncodeFn fn, CUtensorMap* m, const void* ptr, int rank, const cuuint64_t* dims, const cuuint64_t* strides, const cuuint32_t* box,
            CUtensorMapSwizzle sw, CUtensorMapDataType dt = CU_TENSOR_MAP_DATA_TYPE_BFLOAT16) {
  const cuuint32_t es[5] = {1, 1, 1, 1, 1};
  fn(m, dt, rank, const_cast<void*>(ptr), dims, strides, box, es, CU_TENSOR_MAP_INTERLEAVE_NONE, sw,
     CU_TENSOR_MAP_L2_PROMOTION_L2_128B, CU_TENSOR_MAP_FLOAT_OOB_FILL_NONE);
}
void encode2d(EncodeFn fn, CUtensorMap* m, const void* ptr, uint64_t cols, uint64_t rows, uint32_t box_rows) {
  const cuuint64_t d[2] = {cols, rows}, s[1] = {cols * 2};
  const cuuint32_t b[2] = {64, box_rows};
  encode(fn, m, ptr, 2, d, s, b, CU_TENSOR_MAP_SWIZZLE_128B);
}

}

extern "C" void kernel_launch(void* const* d_in, const int* in_sizes, int n_in, void* d_out, int out_size) {
  static EncodeFn fn = nullptr;
  static Scratch* scratch = nullptr;
  if (!fn) {
    cudaGetSymbolAddress((void**)&scratch, g_scratch);
    void* f = nullptr;
    cudaDriverEntryPointQueryResult st;
    cudaGetDriverEntryPoint("cuTensorMapEncodeTiled", &f, cudaEnableDefault, &st);
    fn = (EncodeFn)f;
    cudaFuncSetAttribute(fused_kernel, cudaFuncAttributeMaxDynamicSharedMemorySize, SMEM_BYTES);
  }
  Params p;
  {
    const cuuint64_t d[5] = {512, 2, 4, 16, 16}, s[4] = {1024, 32 * 1024, 2 * 1024, 128 * 1024};
    const cuuint32_t b[5] = {64, 2, 4, 8, 1};
    encode(fn, &p.tm_x, d_in[0], 5, d, s, b, CU_TENSOR_MAP_SWIZZLE_128B);
  }
  {
    const char *re = (const char*)d_in[3], *im = (const char*)d_in[4];
    const uint64_t dist = re < im ? (uint64_t)(im - re) : (uint64_t)(re - im);
    p.bmode = (dist % 16 != 0 || dist >= (1ull << 40) || FORCE_BMODE2) ? 2 : (re < im ? 0 : 1);
    encode2d(fn, &p.tm_b2, im, 512, 512, 8);
    if (p.bmode == 2) encode2d(fn, &p.tm_b, re, 512, 512, 8);
    else {
      const cuuint64_t d[4] = {512, 8, 2, 64}, s[3] = {1024, dist, 8192};
      const cuuint32_t b[4] = {64, 8, 2, 8};
      encode(fn, &p.tm_b, re < im ? re : im, 4, d, s, b, CU_TENSOR_MAP_SWIZZLE_128B);
    }
  }
  encode2d(fn, &p.tm_cre, d_in[5], 512, 512, 64);
  encode2d(fn, &p.tm_cim, d_in[6], 512, 512, 64);
  {
    const cuuint64_t d[3] = {64, 512, 28}, s[2] = {3584, 128};
    const cuuint32_t b[3] = {64, 32, 2};
    encode(fn, &p.tm_w1a, d_in[10], 3, d, s, b, CU_TENSOR_MAP_SWIZZLE_128B);
  }
  {
    const cuuint64_t d[3] = {32, 512, 56}, s[2] = {3584, 64};
    const cuuint32_t b[3] = {32, 64, 3};
    encode(fn, &p.tm_w1b, d_in[10], 3, d, s, b, CU_TENSOR_MAP_SWIZZLE_64B);
  }
  encode2d(fn, &p.tm_w2a, d_in[12], 512, 1792, 128);
  encode2d(fn, &p.tm_w2b, d_in[12], 512, 1792, 96);
  {
    const cuuint64_t d[5] = {512, 2, 4, 16, 16}, s[4] = {2048, 32 * 2048, 2 * 2048, 128 * 2048};
    const cuuint32_t b[5] = {32, 2, 4, 2, 1};
    encode(fn, &p.tm_out, d_out, 5, d, s, b, CU_TENSOR_MAP_SWIZZLE_128B, CU_TENSOR_MAP_DATA_TYPE_FLOAT32);
  }
  p.bre = (const __nv_bfloat16*)d_in[3];
  p.bim = (const __nv_bfloat16*)d_in[4];
  p.epoch = scratch->epoch;
  p.carry = scratch->carry;
  p.gate = scratch->gate;
  p.part = scratch->part;
  p.lam_re = (const __nv_bfloat16*)d_in[1];
  p.lam_im = (const __nv_bfloat16*)d_in[2];
  p.log_dt = (const __nv_bfloat16*)d_in[7];
  p.dskip = (const __nv_bfloat16*)d_in[8];
  p.b1 = (const __nv_bfloat16*)d_in[11];
  p.gate_w = (const __nv_bfloat16*)d_in[13];
  p.w1 = (const __nv_bfloat16*)d_in[10];
  p.w2 = (const __nv_bfloat16*)d_in[12];
  p.cre = (const __nv_bfloat16*)d_in[5];
  p.cim = (const __nv_bfloat16*)d_in[6];
  fused_kernel<<<128, 384, SMEM_BYTES, cudaStreamPerThread>>>(p);
}
```
